```python
import torch

def _softmax(x, axis=-1):
    return torch.softmax(x, dim=axis)
def _gelu(x):
    return torch.nn.functional.gelu(x, approximate="tanh")
def _silu(x):
    return torch.nn.functional.silu(x)
def _sigmoid(x):
    return torch.sigmoid(x)
def _layernorm(x, axis=-1, eps=1e-5):
    m = x.mean(dim=axis, keepdim=True)
    v = x.var(dim=axis, keepdim=True, unbiased=False)
    return (x - m) / torch.sqrt(v + eps)
def _scatter_add(tgt, idx, src, axis=0):
    return tgt.clone().index_add_(axis, idx, src)
def _segment_sum(src, seg, n):
    out = torch.zeros((n,) + src.shape[1:], dtype=src.dtype)
    return out.index_add_(0, seg, src)
def _pad(x, pw):
    flat = tuple(v for pair in reversed(pw) for v in pair)
    return torch.nn.functional.pad(x, flat)

kernel_name = 'sequential_preLN__ssm_conv_h3__dense_activation_squared_relu__prompt'

def setup_inputs():

    _w = (lambda a: (lambda t: t.to(torch.bfloat16) if t.is_floating_point() else t)(torch.as_tensor(a)))
    def _A_setup():
        B, S, D = 1, 2048, 1024
        ks = 4
        return {
            "q": _w((lambda *s: torch.randn(*s, dtype=torch.bfloat16) * 0.05)(B, S, D)),
            "k": _w((lambda *s: torch.randn(*s, dtype=torch.bfloat16) * 0.4)(B, S, D)),
            "v": _w((lambda *s: torch.randn(*s, dtype=torch.bfloat16) * 0.4)(B, S, D)),
            "shift_k": _w((lambda *s: torch.randn(*s, dtype=torch.bfloat16) * 0.4)(D, ks) * 0.5),
            "ssm_k": _w((lambda *s: torch.randn(*s, dtype=torch.bfloat16) * 0.4)(D, S) * (1.0 / S ** 0.5)),
            "ssm_D": _w((lambda *s: torch.randn(*s, dtype=torch.bfloat16) * 0.4)(D)),
        }
    _A_in = _A_setup()

    def _B_setup():
        B, S, D, F = 1, 2048, 1024, 3584
        return {
            "x": _w((lambda *s: torch.randn(*s, dtype=torch.bfloat16) * 0.05)(B, S, D)),
            "w1": _w((lambda *s: torch.randn(*s, dtype=torch.bfloat16) * 0.05)(D, F)),
            "b1": _w((lambda *s: torch.randn(*s, dtype=torch.bfloat16) * 0.4)(F)),
            "w2": _w((lambda *s: torch.randn(*s, dtype=torch.bfloat16) * 0.05)(F, D)),
            "b2": _w((lambda *s: torch.randn(*s, dtype=torch.bfloat16) * 3.2)(D)),
        }
    _B_in = _B_setup()

    return {
        "A_q": _A_in["q"],
        "A_k": _A_in["k"],
        "A_v": _A_in["v"],
        "A_shift_k": _A_in["shift_k"],
        "A_ssm_k": _A_in["ssm_k"],
        "A_ssm_D": _A_in["ssm_D"],
        "B_x": _B_in["x"],
        "B_w1": _B_in["w1"],
        "B_b1": _B_in["b1"],
        "B_w2": _B_in["w2"],
        "B_b2": _B_in["b2"],
    }

def reference(A_q, A_k, A_v, A_shift_k, A_ssm_k, A_ssm_D, B_x, B_w1, B_b1, B_w2, B_b2):
    def _A_ref(q, k, v, shift_k, ssm_k, ssm_D):
        B, S, D = q.shape
        ks = shift_k.shape[-1]
        k_pad = _pad(k, ((0, 0), (ks - 1, 0), (0, 0)))
        k_shift = torch.zeros_like(k)
        for t in range(ks):
            k_shift = k_shift + k_pad[:, t:t + S, :] * shift_k[:, ks - 1 - t][None, None, :]
        kv = k_shift * v
        L = 2 * S
        kv_pad = _pad(kv, ((0, 0), (0, S), (0, 0)))
        kf_pad = _pad(ssm_k, ((0, 0), (0, S)))
        kv_f = (lambda x, axes=(-2,-1): torch.fft.rfft2(x.float(), dim=axes))(kv_pad[:, None, :, :], axes=(1, 2))
        kf_f = (lambda x, axes=(-2,-1): torch.fft.rfft2(x.float(), dim=axes))(kf_pad[:, None, :], axes=(1, 2))
        kf_f = (lambda x, *d: x.permute(*d))(kf_f, 1, 2, 0)
        y_f = kv_f * kf_f[None, :, :, :]
        y = (lambda x, s, axes=(-2,-1): torch.fft.irfft2(x, s=s, dim=axes).to(torch.bfloat16))(y_f, (1, L), axes=(1, 2))[:, 0, :S, :]
        y = y + kv * ssm_D[None, None, :]
        return q * y

    def _B_ref(x, w1, b1, w2, b2):
        h = torch.einsum("bsd,df->bsf", x, w1) + b1
        zero = torch.zeros_like(h)
        r = torch.where(h > zero, h, zero)
        h = r * r
        out = torch.einsum("bsf,fd->bsd", h, w2) + b2
        return out

    x = A_q
    h = x + _A_ref(_layernorm(x, axis=-1), A_k, A_v, A_shift_k, A_ssm_k, A_ssm_D)
    h2 = h + _B_ref(_layernorm(h, axis=-1), B_w1, B_b1, B_w2, B_b2)
    return h2
```

```cpp
#include <cuda_runtime.h>
#include <cuda_bf16.h>
#include <cuda.h>
#include <stdint.h>

namespace {

constexpr int S_ = 2048, D_ = 1024, F_ = 3584;
constexpr int NCTA = 128, NXTRA = 4, NTHREADS = 512;
constexpr float LN_EPS = 1e-5f;
constexpr int CS_DELAY = 5500, W2_GAP = 250, RES_GAP = 400, Q_GAP = 200;
constexpr int KV_AHEAD = 4, X_AFTER = 3, LN1_STEP = 9;
constexpr int R1_EVERY = 9  , RES_END = 50, TAIL_HOLD = 52, TAIL_GO = 55, LEAD = 1;

__device__ __align__(1024) __nv_bfloat16 g_hT[D_ * S_];
__device__ __align__(1024) __nv_bfloat16 g_r[S_ * F_];
__device__ __align__(128) __nv_bfloat16 g_ln1[2 * S_];
__device__ __align__(128) float2 g_st2[NCTA * 128];
__device__ __align__(128) unsigned g_slot[NCTA];
__device__ __align__(128) float g_cs[F_];
constexpr int C_LN1 = 0, C_CS = 1  , C_R = 9  , C_H = 73  , C_ST = 89  , C_NUM = 105;
__device__ __align__(128) unsigned g_cnt[C_NUM * 32];

constexpr int RAW_TX = 33 * 9 * 32, RAWCH = 9600;
constexpr int Q_CH = 32 * 9 * 16;
constexpr int W_PITCH = 8192 + 128, K_PAD = 384, K_PITCH = 4096 + K_PAD, P_K = 4 * W_PITCH, P_SZ = P_K + 4 * K_PITCH;
constexpr int SM_R0 = 0;
constexpr int SM_P0 = SM_R0 + 4 * RAWCH;
constexpr int SM_RX = SM_P0 + P_SZ;
constexpr int SM_PL1 = 98304;
constexpr int SM_Q = SM_PL1 + P_K;
constexpr int SM_ST = SM_Q + 4 * Q_CH + 2 * RAWCH;
constexpr int SM_P1 = SM_ST + 8192;
constexpr int SM_BAR = 229888;
constexpr int SM_ID = SM_BAR + 504, SM_B2 = SM_BAR + 512, SM_END = SM_B2 + 512;
constexpr int STAGE = 49152, NSTAGE = 4, STAGE2 = 32768, NSTAGE2 = 6;
constexpr int SM_CSB = NSTAGE * STAGE, SM_RST = SM_CSB + 448 * 8, SM_RSF = SM_RST + 4096;
constexpr int SMEM_BYTES = SM_END;
static_assert(SM_PL1 >= 2 * STAGE && SM_RSF + 2048 <= SM_BAR && SMEM_BYTES <= 232448, "smem map");
static_assert(SM_Q % 128 == 0 && SM_P0 % 128 == 0 && SM_P1 % 128 == 0 && SM_RX + 4 * RAWCH <= SM_Q && SM_P1 + P_K + 2 * RAWCH <= SM_BAR, "smem map");
__device__ __forceinline__ constexpr int raw_off(int n) { return n == 4 ? SM_P1 + P_K : n == 5 ? SM_Q + 4 * Q_CH : ((n & 2) ? SM_RX : SM_R0) + (n & 1) * 2 * RAWCH; }
constexpr int SM_X0 = SM_RX + 4 * RAWCH, SM_X1 = SM_ST, SM_X2 = SM_R0 + P_K;
static_assert(SM_X0 + 10 * 2048 <= SM_Q + 4 * Q_CH && SM_X2 + 2 * 2048 <= SM_P0, "smem map");
constexpr int B_RAW = 0  , B_KF = 8  , B_Q = 11, B_U = 12  , B_FULL = 20  , B_FULL2 = 24  ,
              B_EMPTY = 30  , B_EMPTY2 = 34  , B_FREE = 40  , B_CSB = 42, B_TOP = 43, B_XD = 44,
              B_RE = 45  , B_CSB1 = 47, B_RES = 48,
              B_DEP = 49  , B_KP = 55  , B_PB = 57, B_D8 = 58, B_ID = 59, B_XR = 60, B_NUM = 61;
static_assert(B_NUM * 8 <= 504, "barriers");
constexpr int NB_EPI = 1, NB_LN = 2, NB_CONS = 3, NB_PUBH = 4  , NB_PUB = 6  ;

struct Params {
  CUtensorMap k3, v3, q3, hT, w1a, w1b, w2, out, r, hR;
  const __nv_bfloat16 *q, *shiftk, *ssmk, *ssmD, *b1, *w2p, *b2;
};

__device__ __forceinline__ uint32_t s2u(const void* p) { return (uint32_t)__cvta_generic_to_shared(p); }
__device__ __forceinline__ void mbar_init(uint32_t bar, uint32_t cnt) { asm volatile("mbarrier.init.shared::cta.b64 [%0], %1;" ::"r"(bar), "r"(cnt) : "memory"); }
__device__ __forceinline__ void mbar_expect_tx(uint32_t bar, uint32_t bytes) { asm volatile("mbarrier.arrive.expect_tx.shared::cta.b64 _, [%0], %1;" ::"r"(bar), "r"(bytes) : "memory"); }
__device__ __forceinline__ void mbar_arrive(uint32_t bar) { asm volatile("mbarrier.arrive.shared::cta.b64 _, [%0];" ::"r"(bar) : "memory"); }
__device__ __forceinline__ void mbar_arrive_cta(uint32_t bar, uint32_t cta) {
  asm volatile("{\n.reg .b32 ra;\nmapa.shared::cluster.u32 ra, %0, %1;\nmbarrier.arrive.shared::cluster.b64 _, [ra];\n}\n" ::"r"(bar), "r"(cta) : "memory");
}
__device__ __forceinline__ void mbar_wait(uint32_t bar, uint32_t parity) {
  uint32_t done, guard = 0;
  do {
    asm volatile("{\n.reg .pred p;\nmbarrier.try_wait.parity.shared::cta.b64 p, [%1], %2;\nselp.u32 %0, 1, 0, p;\n}\n" : "=r"(done) : "r"(bar), "r"(parity) : "memory");
    if (++guard > (1u << 20)) break;
  } while (!done);
}
__device__ __forceinline__ void mbar_sleep(uint32_t bar, uint32_t parity) {
  uint32_t done, guard = 0;
  do {
    asm volatile("{\n.reg .pred p;\nmbarrier.try_wait.parity.shared::cta.b64 p, [%1], %2, %3;\nselp.u32 %0, 1, 0, p;\n}\n" : "=r"(done) : "r"(bar), "r"(parity), "r"(20000) : "memory");
    if (++guard > (1u << 16)) break;
  } while (!done);
}
__device__ __forceinline__ void nbar_sync(int id, int n) { asm volatile("bar.sync %0, %1;" ::"r"(id), "r"(n) : "memory"); }
__device__ __forceinline__ void nbar_arrive(int id, int n) { asm volatile("bar.arrive %0, %1;" ::"r"(id), "r"(n) : "memory"); }
__device__ __forceinline__ bool elect_one() { uint32_t p; asm volatile("{\n.reg .pred P;\nelect.sync _|P, 0xffffffff;\nselp.u32 %0, 1, 0, P;\n}\n" : "=r"(p)); return p != 0; }
__device__ __forceinline__ void fence_async_smem() { asm volatile("fence.proxy.async.shared::cta;" ::: "memory"); }
__device__ __forceinline__ void fence_async_gmem() { asm volatile("fence.proxy.async.global;" ::: "memory"); }
__device__ __forceinline__ void cnt_arrive(int c) { asm volatile("red.release.gpu.global.add.u32 [%0], 1;" ::"l"(&g_cnt[c * 32]) : "memory"); }
__device__ __forceinline__ unsigned cnt_peek(int c, int vz) { unsigned v; asm volatile("ld.relaxed.gpu.global.u32 %0, [%1];" : "=r"(v) : "l"(&g_cnt[c * 32] + vz) : "memory"); return v; }
__device__ __forceinline__ unsigned late_epoch(unsigned v) { unsigned r; asm volatile("shr.u32 %0, %1, 4;" : "=r"(r) : "r"(v)); return r + 1; }
__device__ __forceinline__ void cnt_wait(int c, unsigned target) {
  unsigned guard = 0;
#pragma unroll 1
  while ((int)(cnt_peek(c, 0) - target) < 0) { if (++guard > (1u << 20)) break; }
  asm volatile("fence.acquire.gpu;" ::: "memory");
}
__device__ __forceinline__ void tma3d(uint32_t dst, const CUtensorMap* m, int c0, int c1, int c2, uint32_t bar) {
  asm volatile("cp.async.bulk.tensor.3d.shared::cluster.global.mbarrier::complete_tx::bytes [%0], [%1, {%3, %4, %5}], [%2];" ::"r"(dst), "l"(m), "r"(bar), "r"(c0), "r"(c1), "r"(c2) : "memory");
}
__device__ __forceinline__ void tma3d_mc(uint32_t dst, const CUtensorMap* m, int c0, int c1, int c2, uint32_t bar) {
  asm volatile("cp.async.bulk.tensor.3d.shared::cluster.global.mbarrier::complete_tx::bytes.multicast::cluster [%0], [%1, {%3, %4, %5}], [%2], %6;" ::"r"(dst), "l"(m), "r"(bar), "r"(c0), "r"(c1), "r"(c2), "h"((uint16_t)3) : "memory");
}
__device__ __forceinline__ void tma4d_mc(uint32_t dst, const CUtensorMap* m, int c0, int c1, int c2, int c3, uint32_t bar) {
  asm volatile("cp.async.bulk.tensor.4d.shared::cluster.global.mbarrier::complete_tx::bytes.multicast::cluster [%0], [%1, {%3, %4, %5, %6}], [%2], %7;" ::"r"(dst), "l"(m), "r"(bar), "r"(c0), "r"(c1), "r"(c2), "r"(c3), "h"((uint16_t)3) : "memory");
}
__device__ __forceinline__ void tma4d(uint32_t dst, const CUtensorMap* m, int c0, int c1, int c2, int c3, uint32_t bar) {
  asm volatile("cp.async.bulk.tensor.4d.shared::cluster.global.mbarrier::complete_tx::bytes [%0], [%1, {%3, %4, %5, %6}], [%2];" ::"r"(dst), "l"(m), "r"(bar), "r"(c0), "r"(c1), "r"(c2), "r"(c3) : "memory");
}
__device__ __forceinline__ void bulk_g2s(uint32_t dst, const void* src, uint32_t bytes, uint32_t bar) {
  asm volatile("cp.async.bulk.shared::cluster.global.mbarrier::complete_tx::bytes [%0], [%1], %2, [%3];" ::"r"(dst), "l"(src), "r"(bytes), "r"(bar) : "memory");
}
__device__ __forceinline__ void tma2d_store(const CUtensorMap* m, int c0, int c1, uint32_t src) {
  asm volatile("cp.async.bulk.tensor.2d.global.shared::cta.bulk_group [%0, {%2, %3}], [%1];" ::"l"(m), "r"(src), "r"(c0), "r"(c1) : "memory");
}
__device__ __forceinline__ void wg_fence() { asm volatile("wgmma.fence.sync.aligned;" ::: "memory"); }
__device__ __forceinline__ void wg_commit() { asm volatile("wgmma.commit_group.sync.aligned;" ::: "memory"); }
template <int N> __device__ __forceinline__ void wg_wait() { asm volatile("wgmma.wait_group.sync.aligned %0;" ::"n"(N) : "memory"); }
__device__ __forceinline__ void anchor8(const float* v, int never) {
  asm volatile("{\n.reg .pred p;\nsetp.lt.s32 p, %8, 0;\n@p st.shared.v4.f32 [%8], {%0,%1,%2,%3};\n@p st.shared.v4.f32 [%8+16], {%4,%5,%6,%7};\n}"
               ::"f"(v[0]), "f"(v[1]), "f"(v[2]), "f"(v[3]), "f"(v[4]), "f"(v[5]), "f"(v[6]), "f"(v[7]), "r"(never) : "memory");
}
template <int N> __device__ __forceinline__ void pin(float (&d)[N]) {
#pragma unroll
  for (int i = 0; i < N; i++) asm volatile("" : "+f"(d[i])::"memory");
}
constexpr uint32_t SB = 1024;
__host__ __device__ constexpr uint64_t desc(uint32_t off, uint32_t lbo, uint32_t sbo, uint32_t sw) {
  return (uint64_t)((SB + off) >> 4) | ((uint64_t)(lbo >> 4) << 16) | ((uint64_t)(sbo >> 4) << 32) | ((uint64_t)sw << 62);
}
__device__ __forceinline__ uint32_t lds32(uint32_t a) { uint32_t v; asm volatile("ld.shared.b32 %0, [%1];" : "=r"(v) : "r"(a) : "memory"); return v; }
__device__ __forceinline__ uint4 lds128(uint32_t a) { uint4 v; asm volatile("ld.shared.v4.b32 {%0,%1,%2,%3}, [%4];" : "=r"(v.x), "=r"(v.y), "=r"(v.z), "=r"(v.w) : "r"(a) : "memory"); return v; }
__device__ __forceinline__ uint2 lds64(uint32_t a) { uint2 v; asm volatile("ld.shared.v2.b32 {%0,%1}, [%2];" : "=r"(v.x), "=r"(v.y) : "r"(a) : "memory"); return v; }
__device__ __forceinline__ float2 lds64f(uint32_t a) { float2 v; asm volatile("ld.shared.v2.f32 {%0,%1}, [%2];" : "=f"(v.x), "=f"(v.y) : "r"(a) : "memory"); return v; }
__device__ __forceinline__ void sts128(uint32_t a, uint4 v) { asm volatile("st.shared.v4.b32 [%0], {%1,%2,%3,%4};" ::"r"(a), "r"(v.x), "r"(v.y), "r"(v.z), "r"(v.w) : "memory"); }
__device__ __forceinline__ void sts64f(uint32_t a, float x, float y) { asm volatile("st.shared.v2.f32 [%0], {%1,%2};" ::"r"(a), "f"(x), "f"(y) : "memory"); }
__device__ __forceinline__ void sts64(uint32_t a, uint32_t x, uint32_t y) { asm volatile("st.shared.v2.b32 [%0], {%1,%2};" ::"r"(a), "r"(x), "r"(y) : "memory"); }
__device__ __forceinline__ void sts32(uint32_t a, uint32_t v) { asm volatile("st.shared.b32 [%0], %1;" ::"r"(a), "r"(v) : "memory"); }
__device__ __forceinline__ void stsm4(uint32_t a, uint32_t r0, uint32_t r1, uint32_t r2, uint32_t r3) {
  asm volatile("stmatrix.sync.aligned.m8n8.x4.shared.b16 [%0], {%1,%2,%3,%4};" ::"r"(a), "r"(r0), "r"(r1), "r"(r2), "r"(r3) : "memory");
}
__device__ __forceinline__ void stsm4t(uint32_t a, uint32_t r0, uint32_t r1, uint32_t r2, uint32_t r3) {
  asm volatile("stmatrix.sync.aligned.m8n8.x4.trans.shared.b16 [%0], {%1,%2,%3,%4};" ::"r"(a), "r"(r0), "r"(r1), "r"(r2), "r"(r3) : "memory");
}
__device__ __forceinline__ void ldsm4t(uint32_t a, uint32_t& r0, uint32_t& r1, uint32_t& r2, uint32_t& r3) {
  asm volatile("ldmatrix.sync.aligned.m8n8.x4.trans.shared.b16 {%0,%1,%2,%3}, [%4];" : "=r"(r0), "=r"(r1), "=r"(r2), "=r"(r3) : "r"(a) : "memory");
}
__device__ __forceinline__ uint32_t pack_bf16(float lo, float hi) { uint32_t r; asm("cvt.rn.bf16x2.f32 %0, %1, %2;" : "=r"(r) : "f"(hi), "f"(lo)); return r; }
__device__ __forceinline__ uint32_t bfma2_relu(uint32_t a, uint32_t b, uint32_t c) { uint32_t r; asm("fma.rn.relu.bf16x2 %0, %1, %2, %3;" : "=r"(r) : "r"(a), "r"(b), "r"(c)); return r; }
__device__ __forceinline__ uint32_t bmul2(uint32_t a, uint32_t b) { uint32_t r; asm("mul.rn.bf16x2 %0, %1, %2;" : "=r"(r) : "r"(a), "r"(b)); return r; }
__device__ __forceinline__ uint32_t bfma2(uint32_t a, uint32_t b, uint32_t c) { uint32_t r; asm("fma.rn.bf16x2 %0, %1, %2, %3;" : "=r"(r) : "r"(a), "r"(b), "r"(c)); return r; }
__device__ __forceinline__ uint32_t badd2(uint32_t a, uint32_t b) { uint32_t r; asm("add.rn.bf16x2 %0, %1, %2;" : "=r"(r) : "r"(a), "r"(b)); return r; }
__device__ __forceinline__ float bf_lo(uint32_t v) { return __uint_as_float(v << 16); }
__device__ __forceinline__ float bf_hi(uint32_t v) { return __uint_as_float(v & 0xffff0000u); }
__device__ __forceinline__ uint32_t u4get(const uint4& v, int i) { return i == 0 ? v.x : i == 1 ? v.y : i == 2 ? v.z : v.w; }

__device__ __forceinline__ void wg_rs32(float (&d)[16], const uint32_t (&a)[4], uint32_t db) {
  asm volatile("{\n.reg .b64 dsc;\nmov.b64 dsc, {%20, 8};\n"
    "wgmma.mma_async.sync.aligned.m64n32k16.f32.bf16.bf16 {%0, %1, %2, %3, %4, %5, %6, %7, %8, %9, %10, %11, %12, %13, %14, %15}, {%16, %17, %18, %19}, dsc, 1, 1, 1, 0;\n}"
    : "+f"(d[0]), "+f"(d[1]), "+f"(d[2]), "+f"(d[3]), "+f"(d[4]), "+f"(d[5]), "+f"(d[6]), "+f"(d[7]), "+f"(d[8]), "+f"(d[9]), "+f"(d[10]), "+f"(d[11]), "+f"(d[12]), "+f"(d[13]), "+f"(d[14]), "+f"(d[15])
    : "r"(a[0]), "r"(a[1]), "r"(a[2]), "r"(a[3]), "r"(db));
}
__device__ __forceinline__ void wg_rs32_first(float (&d)[16], const uint32_t (&a)[4], uint32_t db) {
  asm volatile("{\n.reg .b64 dsc;\nmov.b64 dsc, {%20, 8};\n"
    "wgmma.mma_async.sync.aligned.m64n32k16.f32.bf16.bf16 {%0, %1, %2, %3, %4, %5, %6, %7, %8, %9, %10, %11, %12, %13, %14, %15}, {%16, %17, %18, %19}, dsc, 0, 1, 1, 0;\n}"
    : "=f"(d[0]), "=f"(d[1]), "=f"(d[2]), "=f"(d[3]), "=f"(d[4]), "=f"(d[5]), "=f"(d[6]), "=f"(d[7]), "=f"(d[8]), "=f"(d[9]), "=f"(d[10]), "=f"(d[11]), "=f"(d[12]), "=f"(d[13]), "=f"(d[14]), "=f"(d[15])
    : "r"(a[0]), "r"(a[1]), "r"(a[2]), "r"(a[3]), "r"(db));
}
template<int N> __device__ __forceinline__ void wg_ss(float (&d)[N/2], uint64_t da, uint64_t db);
template<> __device__ __forceinline__ void wg_ss<192>(float (&d)[96], uint64_t da, uint64_t db) {
  asm volatile("wgmma.mma_async.sync.aligned.m64n192k16.f32.bf16.bf16 {%0, %1, %2, %3, %4, %5, %6, %7, %8, %9, %10, %11, %12, %13, %14, %15, %16, %17, %18, %19, %20, %21, %22, %23, %24, %25, %26, %27, %28, %29, %30, %31, %32, %33, %34, %35, %36, %37, %38, %39, %40, %41, %42, %43, %44, %45, %46, %47, %48, %49, %50, %51, %52, %53, %54, %55, %56, %57, %58, %59, %60, %61, %62, %63, %64, %65, %66, %67, %68, %69, %70, %71, %72, %73, %74, %75, %76, %77, %78, %79, %80, %81, %82, %83, %84, %85, %86, %87, %88, %89, %90, %91, %92, %93, %94, %95}, %96, %97, 1, 1, 1, 1, 1;"
    : "+f"(d[0]), "+f"(d[1]), "+f"(d[2]), "+f"(d[3]), "+f"(d[4]), "+f"(d[5]), "+f"(d[6]), "+f"(d[7]), "+f"(d[8]), "+f"(d[9]), "+f"(d[10]), "+f"(d[11]), "+f"(d[12]), "+f"(d[13]), "+f"(d[14]), "+f"(d[15]), "+f"(d[16]), "+f"(d[17]), "+f"(d[18]), "+f"(d[19]), "+f"(d[20]), "+f"(d[21]), "+f"(d[22]), "+f"(d[23]), "+f"(d[24]), "+f"(d[25]), "+f"(d[26]), "+f"(d[27]), "+f"(d[28]), "+f"(d[29]), "+f"(d[30]), "+f"(d[31]), "+f"(d[32]), "+f"(d[33]), "+f"(d[34]), "+f"(d[35]), "+f"(d[36]), "+f"(d[37]), "+f"(d[38]), "+f"(d[39]), "+f"(d[40]), "+f"(d[41]), "+f"(d[42]), "+f"(d[43]), "+f"(d[44]), "+f"(d[45]), "+f"(d[46]), "+f"(d[47]), "+f"(d[48]), "+f"(d[49]), "+f"(d[50]), "+f"(d[51]), "+f"(d[52]), "+f"(d[53]), "+f"(d[54]), "+f"(d[55]), "+f"(d[56]), "+f"(d[57]), "+f"(d[58]), "+f"(d[59]), "+f"(d[60]), "+f"(d[61]), "+f"(d[62]), "+f"(d[63]), "+f"(d[64]), "+f"(d[65]), "+f"(d[66]), "+f"(d[67]), "+f"(d[68]), "+f"(d[69]), "+f"(d[70]), "+f"(d[71]), "+f"(d[72]), "+f"(d[73]), "+f"(d[74]), "+f"(d[75]), "+f"(d[76]), "+f"(d[77]), "+f"(d[78]), "+f"(d[79]), "+f"(d[80]), "+f"(d[81]), "+f"(d[82]), "+f"(d[83]), "+f"(d[84]), "+f"(d[85]), "+f"(d[86]), "+f"(d[87]), "+f"(d[88]), "+f"(d[89]), "+f"(d[90]), "+f"(d[91]), "+f"(d[92]), "+f"(d[93]), "+f"(d[94]), "+f"(d[95])
    : "l"(da), "l"(db));
}
template<> __device__ __forceinline__ void wg_ss<128>(float (&d)[64], uint64_t da, uint64_t db) {
  asm volatile("wgmma.mma_async.sync.aligned.m64n128k16.f32.bf16.bf16 {%0, %1, %2, %3, %4, %5, %6, %7, %8, %9, %10, %11, %12, %13, %14, %15, %16, %17, %18, %19, %20, %21, %22, %23, %24, %25, %26, %27, %28, %29, %30, %31, %32, %33, %34, %35, %36, %37, %38, %39, %40, %41, %42, %43, %44, %45, %46, %47, %48, %49, %50, %51, %52, %53, %54, %55, %56, %57, %58, %59, %60, %61, %62, %63}, %64, %65, 1, 1, 1, 0, 1;"
    : "+f"(d[0]), "+f"(d[1]), "+f"(d[2]), "+f"(d[3]), "+f"(d[4]), "+f"(d[5]), "+f"(d[6]), "+f"(d[7]), "+f"(d[8]), "+f"(d[9]), "+f"(d[10]), "+f"(d[11]), "+f"(d[12]), "+f"(d[13]), "+f"(d[14]), "+f"(d[15]), "+f"(d[16]), "+f"(d[17]), "+f"(d[18]), "+f"(d[19]), "+f"(d[20]), "+f"(d[21]), "+f"(d[22]), "+f"(d[23]), "+f"(d[24]), "+f"(d[25]), "+f"(d[26]), "+f"(d[27]), "+f"(d[28]), "+f"(d[29]), "+f"(d[30]), "+f"(d[31]), "+f"(d[32]), "+f"(d[33]), "+f"(d[34]), "+f"(d[35]), "+f"(d[36]), "+f"(d[37]), "+f"(d[38]), "+f"(d[39]), "+f"(d[40]), "+f"(d[41]), "+f"(d[42]), "+f"(d[43]), "+f"(d[44]), "+f"(d[45]), "+f"(d[46]), "+f"(d[47]), "+f"(d[48]), "+f"(d[49]), "+f"(d[50]), "+f"(d[51]), "+f"(d[52]), "+f"(d[53]), "+f"(d[54]), "+f"(d[55]), "+f"(d[56]), "+f"(d[57]), "+f"(d[58]), "+f"(d[59]), "+f"(d[60]), "+f"(d[61]), "+f"(d[62]), "+f"(d[63])
    : "l"(da), "l"(db));
}
__device__ __forceinline__ void wg_ss128t(float (&d)[64], uint64_t da, uint64_t db) {
  asm volatile("wgmma.mma_async.sync.aligned.m64n128k16.f32.bf16.bf16 {%0, %1, %2, %3, %4, %5, %6, %7, %8, %9, %10, %11, %12, %13, %14, %15, %16, %17, %18, %19, %20, %21, %22, %23, %24, %25, %26, %27, %28, %29, %30, %31, %32, %33, %34, %35, %36, %37, %38, %39, %40, %41, %42, %43, %44, %45, %46, %47, %48, %49, %50, %51, %52, %53, %54, %55, %56, %57, %58, %59, %60, %61, %62, %63}, %64, %65, 1, 1, 1, 1, 1;"
    : "+f"(d[0]), "+f"(d[1]), "+f"(d[2]), "+f"(d[3]), "+f"(d[4]), "+f"(d[5]), "+f"(d[6]), "+f"(d[7]), "+f"(d[8]), "+f"(d[9]), "+f"(d[10]), "+f"(d[11]), "+f"(d[12]), "+f"(d[13]), "+f"(d[14]), "+f"(d[15]), "+f"(d[16]), "+f"(d[17]), "+f"(d[18]), "+f"(d[19]), "+f"(d[20]), "+f"(d[21]), "+f"(d[22]), "+f"(d[23]), "+f"(d[24]), "+f"(d[25]), "+f"(d[26]), "+f"(d[27]), "+f"(d[28]), "+f"(d[29]), "+f"(d[30]), "+f"(d[31]), "+f"(d[32]), "+f"(d[33]), "+f"(d[34]), "+f"(d[35]), "+f"(d[36]), "+f"(d[37]), "+f"(d[38]), "+f"(d[39]), "+f"(d[40]), "+f"(d[41]), "+f"(d[42]), "+f"(d[43]), "+f"(d[44]), "+f"(d[45]), "+f"(d[46]), "+f"(d[47]), "+f"(d[48]), "+f"(d[49]), "+f"(d[50]), "+f"(d[51]), "+f"(d[52]), "+f"(d[53]), "+f"(d[54]), "+f"(d[55]), "+f"(d[56]), "+f"(d[57]), "+f"(d[58]), "+f"(d[59]), "+f"(d[60]), "+f"(d[61]), "+f"(d[62]), "+f"(d[63])
    : "l"(da), "l"(db));
}
template<> __device__ __forceinline__ void wg_ss<8>(float (&d)[4], uint64_t da, uint64_t db) {
  asm volatile("wgmma.mma_async.sync.aligned.m64n8k16.f32.bf16.bf16 {%0, %1, %2, %3}, %4, %5, 1, 1, 1, 1, 0;"
    : "+f"(d[0]), "+f"(d[1]), "+f"(d[2]), "+f"(d[3])
    : "l"(da), "l"(db));
}
__device__ __forceinline__ void wg_ss192_first(float (&d)[96], uint64_t da, uint64_t db) {
  asm volatile("wgmma.mma_async.sync.aligned.m64n192k16.f32.bf16.bf16 {%0, %1, %2, %3, %4, %5, %6, %7, %8, %9, %10, %11, %12, %13, %14, %15, %16, %17, %18, %19, %20, %21, %22, %23, %24, %25, %26, %27, %28, %29, %30, %31, %32, %33, %34, %35, %36, %37, %38, %39, %40, %41, %42, %43, %44, %45, %46, %47, %48, %49, %50, %51, %52, %53, %54, %55, %56, %57, %58, %59, %60, %61, %62, %63, %64, %65, %66, %67, %68, %69, %70, %71, %72, %73, %74, %75, %76, %77, %78, %79, %80, %81, %82, %83, %84, %85, %86, %87, %88, %89, %90, %91, %92, %93, %94, %95}, %96, %97, 0, 1, 1, 1, 1;"
    : "=f"(d[0]), "=f"(d[1]), "=f"(d[2]), "=f"(d[3]), "=f"(d[4]), "=f"(d[5]), "=f"(d[6]), "=f"(d[7]), "=f"(d[8]), "=f"(d[9]), "=f"(d[10]), "=f"(d[11]), "=f"(d[12]), "=f"(d[13]), "=f"(d[14]), "=f"(d[15]), "=f"(d[16]), "=f"(d[17]), "=f"(d[18]), "=f"(d[19]), "=f"(d[20]), "=f"(d[21]), "=f"(d[22]), "=f"(d[23]), "=f"(d[24]), "=f"(d[25]), "=f"(d[26]), "=f"(d[27]), "=f"(d[28]), "=f"(d[29]), "=f"(d[30]), "=f"(d[31]), "=f"(d[32]), "=f"(d[33]), "=f"(d[34]), "=f"(d[35]), "=f"(d[36]), "=f"(d[37]), "=f"(d[38]), "=f"(d[39]), "=f"(d[40]), "=f"(d[41]), "=f"(d[42]), "=f"(d[43]), "=f"(d[44]), "=f"(d[45]), "=f"(d[46]), "=f"(d[47]), "=f"(d[48]), "=f"(d[49]), "=f"(d[50]), "=f"(d[51]), "=f"(d[52]), "=f"(d[53]), "=f"(d[54]), "=f"(d[55]), "=f"(d[56]), "=f"(d[57]), "=f"(d[58]), "=f"(d[59]), "=f"(d[60]), "=f"(d[61]), "=f"(d[62]), "=f"(d[63]), "=f"(d[64]), "=f"(d[65]), "=f"(d[66]), "=f"(d[67]), "=f"(d[68]), "=f"(d[69]), "=f"(d[70]), "=f"(d[71]), "=f"(d[72]), "=f"(d[73]), "=f"(d[74]), "=f"(d[75]), "=f"(d[76]), "=f"(d[77]), "=f"(d[78]), "=f"(d[79]), "=f"(d[80]), "=f"(d[81]), "=f"(d[82]), "=f"(d[83]), "=f"(d[84]), "=f"(d[85]), "=f"(d[86]), "=f"(d[87]), "=f"(d[88]), "=f"(d[89]), "=f"(d[90]), "=f"(d[91]), "=f"(d[92]), "=f"(d[93]), "=f"(d[94]), "=f"(d[95])
    : "l"(da), "l"(db));
}
__device__ __forceinline__ void wg_ss128_first(float (&d)[64], uint64_t da, uint64_t db) {
  asm volatile("wgmma.mma_async.sync.aligned.m64n128k16.f32.bf16.bf16 {%0, %1, %2, %3, %4, %5, %6, %7, %8, %9, %10, %11, %12, %13, %14, %15, %16, %17, %18, %19, %20, %21, %22, %23, %24, %25, %26, %27, %28, %29, %30, %31, %32, %33, %34, %35, %36, %37, %38, %39, %40, %41, %42, %43, %44, %45, %46, %47, %48, %49, %50, %51, %52, %53, %54, %55, %56, %57, %58, %59, %60, %61, %62, %63}, %64, %65, 0, 1, 1, 0, 1;"
    : "=f"(d[0]), "=f"(d[1]), "=f"(d[2]), "=f"(d[3]), "=f"(d[4]), "=f"(d[5]), "=f"(d[6]), "=f"(d[7]), "=f"(d[8]), "=f"(d[9]), "=f"(d[10]), "=f"(d[11]), "=f"(d[12]), "=f"(d[13]), "=f"(d[14]), "=f"(d[15]), "=f"(d[16]), "=f"(d[17]), "=f"(d[18]), "=f"(d[19]), "=f"(d[20]), "=f"(d[21]), "=f"(d[22]), "=f"(d[23]), "=f"(d[24]), "=f"(d[25]), "=f"(d[26]), "=f"(d[27]), "=f"(d[28]), "=f"(d[29]), "=f"(d[30]), "=f"(d[31]), "=f"(d[32]), "=f"(d[33]), "=f"(d[34]), "=f"(d[35]), "=f"(d[36]), "=f"(d[37]), "=f"(d[38]), "=f"(d[39]), "=f"(d[40]), "=f"(d[41]), "=f"(d[42]), "=f"(d[43]), "=f"(d[44]), "=f"(d[45]), "=f"(d[46]), "=f"(d[47]), "=f"(d[48]), "=f"(d[49]), "=f"(d[50]), "=f"(d[51]), "=f"(d[52]), "=f"(d[53]), "=f"(d[54]), "=f"(d[55]), "=f"(d[56]), "=f"(d[57]), "=f"(d[58]), "=f"(d[59]), "=f"(d[60]), "=f"(d[61]), "=f"(d[62]), "=f"(d[63])
    : "l"(da), "l"(db));
}
__device__ __forceinline__ void wg_ss128t_first(float (&d)[64], uint64_t da, uint64_t db) {
  asm volatile("wgmma.mma_async.sync.aligned.m64n128k16.f32.bf16.bf16 {%0, %1, %2, %3, %4, %5, %6, %7, %8, %9, %10, %11, %12, %13, %14, %15, %16, %17, %18, %19, %20, %21, %22, %23, %24, %25, %26, %27, %28, %29, %30, %31, %32, %33, %34, %35, %36, %37, %38, %39, %40, %41, %42, %43, %44, %45, %46, %47, %48, %49, %50, %51, %52, %53, %54, %55, %56, %57, %58, %59, %60, %61, %62, %63}, %64, %65, 0, 1, 1, 1, 1;"
    : "=f"(d[0]), "=f"(d[1]), "=f"(d[2]), "=f"(d[3]), "=f"(d[4]), "=f"(d[5]), "=f"(d[6]), "=f"(d[7]), "=f"(d[8]), "=f"(d[9]), "=f"(d[10]), "=f"(d[11]), "=f"(d[12]), "=f"(d[13]), "=f"(d[14]), "=f"(d[15]), "=f"(d[16]), "=f"(d[17]), "=f"(d[18]), "=f"(d[19]), "=f"(d[20]), "=f"(d[21]), "=f"(d[22]), "=f"(d[23]), "=f"(d[24]), "=f"(d[25]), "=f"(d[26]), "=f"(d[27]), "=f"(d[28]), "=f"(d[29]), "=f"(d[30]), "=f"(d[31]), "=f"(d[32]), "=f"(d[33]), "=f"(d[34]), "=f"(d[35]), "=f"(d[36]), "=f"(d[37]), "=f"(d[38]), "=f"(d[39]), "=f"(d[40]), "=f"(d[41]), "=f"(d[42]), "=f"(d[43]), "=f"(d[44]), "=f"(d[45]), "=f"(d[46]), "=f"(d[47]), "=f"(d[48]), "=f"(d[49]), "=f"(d[50]), "=f"(d[51]), "=f"(d[52]), "=f"(d[53]), "=f"(d[54]), "=f"(d[55]), "=f"(d[56]), "=f"(d[57]), "=f"(d[58]), "=f"(d[59]), "=f"(d[60]), "=f"(d[61]), "=f"(d[62]), "=f"(d[63])
    : "l"(da), "l"(db));
}


__device__ __forceinline__ void conv_lda(uint32_t (&a)[2][4], uint32_t we, uint32_t wo, int T) {
#pragma unroll
  for (int c = 0; c < 2; c++) {
    const int o = c * W_PITCH + T * 512;
    a[c][0] = lds32(wo + o); a[c][1] = lds32(wo + o + 256); a[c][2] = lds32(we + o); a[c][3] = lds32(we + o + 256);
  }
}
__device__ __forceinline__ void conv_flush(float (&d)[16], float& c0, float& c1, uint32_t addr) {
  pin(d);
  stsm4t(addr, pack_bf16(d[0] + c0, d[1] + c1), pack_bf16(d[4] + d[2], d[5] + d[3]), pack_bf16(d[8] + d[6], d[9] + d[7]), pack_bf16(d[12] + d[10], d[13] + d[11]));
  asm volatile("mov.f32 %0, %2;\nmov.f32 %1, %3;" : "=f"(c0), "=f"(c1) : "f"(d[14]), "f"(d[15]));
}
struct ConvArgs {
  uint32_t we, wo, kd;
  uint32_t ubar;
  uint32_t pb, pb2;
};
template <int J0, int T>
struct ConvSteps {
  static constexpr int NT = 2 * J0 + 8;
  template <class F>
  static __device__ __forceinline__ void run(float (&d)[2][4][16], uint32_t (&a)[3][2][4], float (&cy)[4], const ConvArgs& A, F&& mid) {
    if (J0 == 4 && T == LN1_STEP) mid();
    constexpr bool late = (T & 1) && (J0 == 0 || T == 7 || T == 13);
    if (T + 1 < NT && !late) {
      if ((T + 1) % 2 == 0 && T + 1 >= 2 * J0) mbar_wait(A.ubar + 8 * ((T + 1) / 2), 0);
      conv_lda(a[(T + 1) % 3], A.we, A.wo, T + 1);
    }
    constexpr int jf = (T >= 3 && (T & 1)) ? (T - 3) / 2 - J0 : -1;
    wg_fence();
#pragma unroll
    for (int c = 0; c < 2; c++) {
#pragma unroll
      for (int j = 0; j < 4; j++)
        if (2 * (J0 + j) + 1 >= T) {
          const uint32_t db = A.kd + (c * (K_PITCH / 16) + 32 * (J0 + j) - 16 * T);
          if (T == 0) wg_rs32_first(d[c][j], a[T % 3][c], db); else wg_rs32(d[c][j], a[T % 3][c], db);
        }
      if (c == 1) wg_commit();
      if (jf >= 0) conv_flush(d[c][jf < 0 ? 0 : jf], cy[2 * c], cy[2 * c + 1], A.pb + (jf < 0 ? 0 : jf) * 2048 + c * W_PITCH);
    }
    if (T + 1 < NT) {
      if (late) {
        mbar_wait(A.ubar + 8 * ((T + 1) / 2), 0);
        conv_lda(a[(T + 1) % 3], A.we, A.wo, T + 1);
      }
      wg_wait<1>();
      ConvSteps<J0, (T + 1 < NT ? T + 1 : T)>::run(d, a, cy, A, mid);
    } else {
      wg_wait<0>();
      conv_flush(d[0][3], cy[0], cy[1], A.pb + 3 * 2048);
      conv_flush(d[1][3], cy[2], cy[3], A.pb + 3 * 2048 + W_PITCH);
    }
  }
};
template <int J0, class F>
__device__ __forceinline__ void conv_pair(float (&cy)[4], const ConvArgs& A, F&& mid) {
  float d[2][4][16];
  uint32_t a[3][2][4];
  if (J0 == 0) mbar_wait(A.ubar, 0);
  conv_lda(a[0], A.we, A.wo, 0);
  ConvSteps<J0, 0>::run(d, a, cy, A, mid);
}
template <int T, int NL>
struct ConvSingle {
  static constexpr int NL1 = (T < 3 ? 2 * T + 2 : T + 5) < 16 ? (T < 3 ? 2 * T + 2 : T + 5) : 16;
  static __device__ __forceinline__ void run(float (&d)[8][16], uint32_t (&a)[6][4], float& c0, float& c1, const ConvArgs& A) {
#pragma unroll
    for (int n = NL; n < NL1; n++) {
      a[n % 6][0] = lds32(A.wo + n * 512); a[n % 6][1] = lds32(A.wo + n * 512 + 256);
      a[n % 6][2] = lds32(A.we + n * 512); a[n % 6][3] = lds32(A.we + n * 512 + 256);
    }
    wg_fence();
#pragma unroll
    for (int j = 0; j < 8; j++)
      if (2 * j + 1 >= T) {
        if (T == 0) wg_rs32_first(d[j], a[T % 6], A.kd + 32 * j); else wg_rs32(d[j], a[T % 6], A.kd + (32 * j - 16 * T));
      }
    wg_commit();
    if (T >= 3 && (T & 1)) {
      constexpr int jf = T >= 3 ? (T - 3) / 2 : 0;
      conv_flush(d[jf], c0, c1, jf < 4 ? A.pb + jf * 2048 : A.pb2 + (jf - 4) * 2048);
    }
    if (T < 15) {
      wg_wait<1>();
      ConvSingle<(T < 15 ? T + 1 : T), NL1>::run(d, a, c0, c1, A);
    } else {
      wg_wait<0>();
      conv_flush(d[7], c0, c1, A.pb2 + 3 * 2048);
    }
  }
};

__device__ constexpr int rs_done(int t) { return t < 6 ? (t == 0 ? 2 : t == 1 ? 6 : t == 2 ? 8 : t == 3 ? 12 : t == 4 ? 14 : 16) : 16 + 2 * (t - 5); }
constexpr int RS_N = 14;
template <int N>
__device__ __forceinline__ void pack_acc(const float (&d)[N], uint32_t (&p)[N / 2]) {
#pragma unroll
  for (int e = 0; e < N / 2; e++) p[e] = pack_bf16(d[2 * e], d[2 * e + 1]);
}
template <int NP>
__device__ __forceinline__ void r_store(const uint32_t (&p)[NP], int q0, int q1, uint32_t csb, const uint4& st, uint8_t* dst) {
#pragma unroll
  for (int q = q0; q < q1; q += 2) {
    const uint4 cb = lds128(csb + q * 32);
#pragma unroll
    for (int e = 0; e < 2; e++) {
      const uint32_t cs = e ? cb.z : cb.x, b1 = e ? cb.w : cb.y;
      const uint32_t a = bfma2_relu(p[2 * (q + e)], st.x, bfma2(st.y, cs, b1)), b = bfma2_relu(p[2 * (q + e) + 1], st.z, bfma2(st.w, cs, b1));
      *reinterpret_cast<uint32_t*>(dst + (q >> 3) * 16384 + ((q + e) & 7) * 128) = bmul2(a, a);
      *reinterpret_cast<uint32_t*>(dst + (q >> 3) * 16384 + ((q + e) & 7) * 128 + 1024) = bmul2(b, b);
    }
  }
}

__device__ __forceinline__ void r_store(const float (&d)[96], int q, uint32_t csb, const uint4& st, uint8_t* dst) {
  uint32_t p[4];
#pragma unroll
  for (int e = 0; e < 4; e++) p[e] = pack_bf16(d[4 * q + 2 * e], d[4 * q + 2 * e + 1]);
  r_store(p, 0, 2, csb + q * 32, st, dst + (q >> 3) * 16384 + (q & 7) * 128);
}

__global__ void __launch_bounds__(NTHREADS, 1) fused_kernel(const __grid_constant__ Params P) {
  extern __shared__ __align__(1024) uint8_t smem_raw[];
  const uint32_t sb = s2u(smem_raw);
  if ((sb & 0x3FFFF) != SB) return;
  const uint32_t bars = sb + SM_BAR;
  const int tid = threadIdx.x, lane = tid & 31;
  const int warp = __shfl_sync(0xffffffff, tid >> 5, 0);
  const int bc = blockIdx.x >> 1;
  const int cl = bc < 4 || bc >= 64 ? bc : bc < 36 ? 4 + ((bc - 4) & 7) * 4 + ((bc - 4) >> 3) : 36 + (bc - 36 - (((bc - 36) * 37) >> 8) * 7) * 4 + (((bc - 36) * 37) >> 8);
  const int cta = cl * 2 + (blockIdx.x & 1);
  const uint32_t rank = cta & 1;

  auto load_filters = [&](int ph) {
    const int bytes = ph == 2 ? 4096 : 2048;
    mbar_expect_tx(bars + 8 * (B_KF + ph), 4 * bytes);
#pragma unroll 1
    for (int c = 0; c < 4; c++)
      bulk_g2s(sb + (ph == 2 ? SM_P1 : SM_P0) + P_K + c * K_PITCH + K_PAD + (ph & 1) * 2048,
               P.ssmk + (size_t)(cta * 8 + (ph >> 1) * 4 + c) * S_ + (ph & 1) * 1024, bytes, bars + 8 * (B_KF + ph));
  };
  auto load_q = [&](int i) { tma3d(sb + SM_Q + i * Q_CH, &P.q3, cta * 8, 0, 32 * i, bars + 8 * B_Q); };
  if (cta >= NCTA) {
    const int x = cta - NCTA;
    if (tid == 0) {
      for (int i = 0; i < NSTAGE2; i++) { mbar_init(bars + 8 * (B_FULL2 + i), 1); mbar_init(bars + 8 * (B_EMPTY2 + i), 1); }
      asm volatile("fence.mbarrier_init.release.cluster;" ::: "memory");
    }
    if (tid < 64) sts32(sb + NSTAGE * STAGE + tid * 4, 0x3f803f80u);
    fence_async_smem();
    __syncthreads();
    if (warp == 4) {
      __nanosleep(CS_DELAY);
      int s = 0, par = 1;
#pragma unroll 1
      for (int n = 0; n < 64; n++) {
        const int t = n >> 5, kb = n & 15;
        mbar_wait(bars + 8 * (B_EMPTY2 + s), par);
        if (elect_one()) {
          mbar_expect_tx(bars + 8 * (B_FULL2 + s), t ? 24576 : 32768);
          for (int hf = 0; hf < 2; hf++)
            tma4d(sb + s * STAGE2 + hf * 16384, t ? &P.w1b : &P.w1a, 0, (kb >> 3) * 4, (kb & 7) * 16 + hf * 8, (2 * x + ((n >> 4) & 1)) * 7 + 4 * t, bars + 8 * (B_FULL2 + s));
        }
        __syncwarp();
        if (++s == NSTAGE2) { s = 0; par ^= 1; }
      }
    } else if (warp < 4) {
      const uint64_t db = desc(NSTAGE * STAGE, 128, 128, 0);
      int s = 0, par = 0;
#pragma unroll 1
      for (int tile = 0; tile < 4; tile++) {
        float d[4][4];
#pragma unroll
        for (int j = 0; j < 4; j++) d[j][0] = d[j][1] = d[j][2] = d[j][3] = 0.f;
#pragma unroll 1
        for (int kb = 0; kb < 16; kb++) {
          mbar_wait(bars + 8 * (B_FULL2 + s), par);
          const uint64_t da = desc(0, 8192, 1024, 1) + s * (STAGE2 / 16);
          wg_fence();
#pragma unroll
          for (int k = 0; k < 4; k++)
#pragma unroll
            for (int j = 0; j < 4; j++) wg_ss<8>(d[j], da + j * 256 + (k >> 1) * 1024 + (k & 1) * 128, db);
          wg_commit();
          wg_wait<0>();
          if (tid == 0) mbar_arrive(bars + 8 * (B_EMPTY2 + s));
          if (++s == NSTAGE2) { s = 0; par ^= 1; }
        }
#pragma unroll
        for (int j = 0; j < 4; j++) pin(d[j]);
        if ((lane & 3) == 0) {
          float* dst = g_cs + (2 * x + (tile & 1)) * 448 + (tile >> 1) * 256 + warp * 16 + (lane >> 2);
#pragma unroll
          for (int j = 0; j < 4; j++)
            if (j < 3 || tile < 2) { dst[j * 64] = d[j][0]; dst[j * 64 + 8] = d[j][2]; }
        }
        if (tile & 1) {
          nbar_sync(1, 128);
          if (tid == 0) cnt_arrive(C_CS + (tile >> 1) * 4 + x);
        }
      }
    }
    return;
  }

  int vz;
  asm volatile("mov.u32 %0, 0;" : "=r"(vz));
#define ep1 late_epoch(epr)
#define TILE_COORDS                                            \
  mbar_wait(bars + 8 * B_ID, 0);                               \
  const int vc = __shfl_sync(0xffffffff, lds32(sb + SM_ID), 0); \
  const int mblk = (vc & 7) * 2 + rank, nblk = vc >> 3;        \
  (void)mblk; (void)nblk

  if (warp >= 8) {
    if (warp < 12) {
    asm volatile("setmaxnreg.dec.sync.aligned.u32 40;");
    if (warp == 8) {
      const bool leader = elect_one();
      if (leader) {
        asm volatile("prefetch.tensormap [%0];" ::"l"(rank ? &P.v3 : &P.k3) : "memory");
#pragma unroll
        for (int i = 0; i <= B_Q; i++) mbar_init(bars + 8 * i, i == B_Q ? 2 : 1);
        mbar_init(bars + 8 * B_XR, 1);
        asm volatile("fence.mbarrier_init.release.cluster;" ::: "memory");
      }
      __syncwarp();
      asm volatile("barrier.cluster.arrive.relaxed.aligned;" ::: "memory");
      auto load_x = [&](int n) {
        bulk_g2s(sb + (n < 2 ? SM_X0 + n * 10240 : SM_X1), P.q + (size_t)(cta * 16 + 5 * n) * D_, (n < 2 ? 5 : 4) * 2048, bars + 8 * B_XR);
        if (n == 2) {
          mbar_wait(bars + 8 * (B_U + 1), 0);
          bulk_g2s(sb + SM_X2, P.q + (size_t)(cta * 16 + 14) * D_, 4096, bars + 8 * B_XR);
        }
      };
      if (leader) {
        load_filters(0);
#pragma unroll
        for (int i = 0; i < 8; i++) mbar_expect_tx(bars + 8 * (B_RAW + i), 2 * RAW_TX);
        mbar_expect_tx(bars + 8 * B_Q, 8 * Q_CH);
        mbar_expect_tx(bars + 8 * B_XR, 32768);
      }
      __syncwarp();
      asm volatile("barrier.cluster.wait.acquire.aligned;" ::: "memory");
      if (leader) {
#pragma unroll 1
        for (int i = 0; i < 8; i++) {
          if (i >= KV_AHEAD) mbar_wait(bars + 8 * (B_RAW + i - KV_AHEAD), 0);
          if (i >= 6) mbar_wait(bars + 8 * (B_RE + i - 6), 0);
          tma3d_mc(sb + raw_off(i) + rank * RAWCH, rank ? &P.v3 : &P.k3, cl * 16, 0, 32 * i - 1, bars + 8 * (B_RAW + i));
          if (i == 3) { load_filters(1); asm volatile("prefetch.tensormap [%0];" ::"l"(&P.q3) : "memory"); }
          if (i >= X_AFTER && i < X_AFTER + 3) load_x(i - X_AFTER);
        }
        mbar_wait(bars + 8 * (B_U + 4), 0);
        load_filters(2);
#pragma unroll 1
        for (int nq = 0; nq < 8; nq++) {
          if ((nq & 3) == 0) mbar_wait(bars + 8 * (nq ? B_XD : B_U + 5), 0);
          load_q(nq ^ 4);
          if (nq) __nanosleep(Q_GAP);
        }
        asm volatile("prefetch.tensormap [%0];" ::"l"(&P.hT) : "memory");
        asm volatile("prefetch.tensormap [%0];" ::"l"(&P.w1a) : "memory");
      }
      __syncwarp();
      TILE_COORDS;
      int it = 0;
#pragma unroll 1
      for (; it < 32; it++) {
        const int s = it & 3, kb = it & 15;
        const uint32_t fb = bars + 8 * (B_FULL + s), st = sb + s * STAGE;
        if (it >= 4) mbar_wait(bars + 8 * (B_EMPTY + s), ((it >> 2) - 1) & 1);
        else mbar_wait(bars + 8 * (B_FREE + (s >> 1)), 0);
        if (it == 0) mbar_wait(bars + 8 * B_PB, 0);
        if (elect_one()) {
          mbar_expect_tx(fb, it < 16 ? 49152 : 40960);
          tma4d_mc(st + 16384 + rank * 16384, it < 16 ? &P.w1a : &P.w1b, 0, (kb >> 3) * 4, (kb & 7) * 16 + rank * 8, nblk * 7 + (it < 16 ? 0 : 4), fb);
        }
        __syncwarp();
        if (it < 2) continue;
        if (it == 2 || it == 8 || it == 9) { mbar_wait(bars + 8 * (it == 8 ? B_D8 : B_DEP + (it >> 3)), 0); fence_async_gmem(); }
        if (elect_one()) {
          tma3d(st, &P.hT, 0, kb * 64, mblk * 2, fb);
          if (it == 9) asm volatile("prefetch.tensormap [%0];" ::"l"(&P.w1b) : "memory");
          if (it == 25) { asm volatile("prefetch.tensormap [%0];" ::"l"(&P.w2) : "memory"); asm volatile("prefetch.tensormap [%0];" ::"l"(&P.r) : "memory"); }
        }
        __syncwarp();
      }
      int s = 0, par = 1;
#pragma unroll 1
      for (int o = 0; o < 56; o++) {
        if (o == 0 || o == 16 || o == 32 || o == 40) { mbar_wait(bars + 8 * (B_DEP + 2 + ((o + 8) >> 4)), 0); fence_async_gmem(); }
        const int kb = (o & 7) * 7 + (o >> 3);
        const uint32_t fb = bars + 8 * (B_FULL2 + s), st = sb + s * STAGE2;
        if (o < NSTAGE2) mbar_wait(bars + 8 * (B_EMPTY + (2 * s + 1) / 3), 1);
        else mbar_wait(bars + 8 * (B_EMPTY2 + s), par);
        if (elect_one()) {
          mbar_expect_tx(fb, 32768);
          tma3d(st, &P.r, 0, 0, mblk * 56 + kb, fb);
          tma3d_mc(st + 16384 + rank * 8192, &P.w2, 0, kb * 64 + rank * 32, nblk * 2, fb);
        }
        __syncwarp();
        if (++s == NSTAGE2) { s = 0; par ^= 1; }
      }
    } else {
      if (elect_one()) {
        if (warp == 9) {
#pragma unroll
          for (int i = B_U; i < B_EMPTY; i++) mbar_init(bars + 8 * i, i < B_FULL ? 2 : 1);
        } else if (warp == 10) {
#pragma unroll
          for (int i = B_EMPTY; i < B_CSB1; i++) mbar_init(bars + 8 * i, i < B_CSB ? 16 : i == B_CSB ? 5 : i == B_TOP ? 2 : i == B_XD ? 8 : 4);
        } else {
#pragma unroll
          for (int i = B_CSB1; i < B_XR; i++) mbar_init(bars + 8 * i, 1);
        }
        asm volatile("fence.mbarrier_init.release.cluster;" ::: "memory");
      }
      __syncwarp();
      asm volatile("barrier.cluster.arrive.relaxed.aligned;" ::: "memory");
      const unsigned short dvr = __ldg(reinterpret_cast<const unsigned short*>(P.ssmD) + cta * 8 + (lane & 7));
      const unsigned epr = cnt_peek(C_H + 8 + (cta >> 4), vz);
      asm volatile("barrier.cluster.wait.acquire.aligned;" ::: "memory");
      if (warp == 11) {
        uint32_t smid;
        asm("mov.u32 %0, %%smid;" : "=r"(smid));
        const int tp = smid >> 1;
        const int want = tp < 32 ? tp : tp < 60 ? (4 + (tp - 32) / 7) * 8 + 1 + (tp - 32) % 7 : tp >= 62 && tp < 66 ? (tp - 58) * 8 : -1;
        if (lane == 0 && want >= 0) g_slot[want * 2 + rank] = ep1 * 64 + cl;
        nbar_sync(NB_LN, 256 + 32);
        if (lane == 0) { fence_async_gmem(); cnt_arrive(C_LN1); }
        cnt_wait(C_LN1, ep1 * NCTA);
        fence_async_gmem();
        if (elect_one()) {
          mbar_expect_tx(bars + 8 * B_Q, 8192);
          bulk_g2s(sb + SM_ST, g_ln1, 8192, bars + 8 * B_Q);
        }
        __syncwarp();
        {
          const uint4 c = __ldcg(reinterpret_cast<const uint4*>(g_slot) + lane);
          const bool ok = __all_sync(0xffffffff, c.x == c.y && c.z == c.w && (c.x >> 6) == (ep1 & 0x3ffffff) && (c.z >> 6) == (ep1 & 0x3ffffff));
          if (lane == 0) { sts32(sb + SM_ID, ok ? want : bc); mbar_arrive(bars + 8 * B_ID); }
          __syncwarp();
        }
        TILE_COORDS;
#pragma unroll 1
        for (int p = 0; p < 2; p++) {
          nbar_sync(NB_PUBH + p, 256 + 32);
          if (lane == 0) { fence_async_gmem(); cnt_arrive(C_H + p * 8 + (cta >> 4)); if (p == 0) mbar_arrive(bars + 8 * B_PB); }
          __syncwarp();
        }
#pragma unroll
        for (int i = 0; i < 2; i++) {
          const int e = i * 32 + lane;
          const uint32_t v = __ldg(reinterpret_cast<const uint32_t*>(P.b2 + nblk * 128) + e);
          sts64f(sb + SM_B2 + (e >> 3) * 64 + (e & 3) * 16 + ((e >> 2) & 1) * 8, bf_lo(v), bf_hi(v));
        }
#pragma unroll 1
        for (int t = 0; t < 2; t++) {
          cnt_wait(C_CS + t * 4 + (nblk >> 1), ep1);
#pragma unroll 1
          for (int i = t * 64 + lane; i < (t ? 112 : 64); i += 32) {
            const float4 a = __ldcg(reinterpret_cast<const float4*>(g_cs + nblk * 448) + i);
            const uint2 b = __ldg(reinterpret_cast<const uint2*>(P.b1 + nblk * 448) + i);
            const uint32_t o = sb + SM_CSB + (i >> 2) * 64 + (i & 1) * 32 + ((i >> 1) & 1) * 8;
            sts64(o, pack_bf16(a.x, a.y), b.x); sts64(o + 16, pack_bf16(a.z, a.w), b.y);
          }
          __syncwarp();
          if (lane == 0) { mbar_arrive(bars + 8 * (t ? B_CSB1 : B_CSB)); }
        }
        if (elect_one()) {
          asm volatile("prefetch.tensormap [%0];" ::"l"(&P.hR) : "memory");
          mbar_sleep(bars + 8 * B_TOP, 0);
          fence_async_gmem();
          mbar_expect_tx(bars + 8 * B_RES, 32768);
#pragma unroll 1
          for (int i = 0; i < 8; i++) {
            tma3d(sb + NSTAGE * STAGE + i * 4096, &P.hR, 0, (i & 1) * 512 + nblk * 64 + (i >> 1) * 16, mblk * 2, bars + 8 * B_RES);
            __nanosleep(RES_GAP);
          }
          asm volatile("prefetch.tensormap [%0];" ::"l"(&P.out) : "memory");
        }
      } else {
        if (warp == 10) {
          const uint4 z = make_uint4(0, 0, 0, 0);
          sts128(sb + SM_P0 + (lane >> 3) * W_PITCH + (lane & 7) * 16, z);
          sts128(sb + SM_P1 + (lane >> 3) * W_PITCH + (lane & 7) * 16, z);
#pragma unroll 1
          for (int ph = 0; ph < 2; ph++) {
            const uint32_t kr = sb + (ph ? SM_P1 : SM_P0) + P_K;
            mbar_sleep(bars + 8 * (B_KF + 2 * ph), 0);
            if (lane < 24) {
#pragma unroll
              for (int c = 0; c < 4; c++) sts128(kr + c * K_PITCH + lane * 16, z);
            }
            if ((lane >> 2) == ph) {
              const uint32_t kc = kr + (lane & 3) * K_PITCH + K_PAD, k01 = lds32(kc);
              sts32(kc, pack_bf16(bf_lo(k01) + bf_lo(dvr), bf_hi(k01)));
            }
            fence_async_smem();
            if (ph) {
              mbar_wait(bars + 8 * B_XD, 0); mbar_wait(bars + 8 * (B_U + 6), 0); mbar_wait(bars + 8 * (B_U + 7), 0);
              if (lane < 8) sts128(sb + ((lane & 4) ? SM_PL1 : SM_R0) + (lane & 3) * W_PITCH + 8192, z);
            }
            __syncwarp();
            if (lane == 0) mbar_arrive(bars + 8 * (B_KP + ph));
          }
          TILE_COORDS;
#pragma unroll 1
          for (int p = 0; p < 2; p++) {
            mbar_sleep(bars + 8 * (B_FREE + p), 0);
            if (p == 0) {
              if (lane < 2) {
                cnt_wait(C_H + lane, ep1 * 16);
                fence_async_gmem();
                tma3d(sb + lane * STAGE, &P.hT, 0, lane * 64, mblk * 2, bars + 8 * (B_FULL + lane));
              }
              __syncwarp();
            }
            if (p == 1) {
              cnt_wait(C_H + 8, ep1 * 16);
              if (lane == 0) mbar_arrive(bars + 8 * B_D8);
            }
            cnt_wait(C_H + p * 8 + (lane & 7), ep1 * 16);
            __syncwarp();
            if (lane == 0) mbar_arrive(bars + 8 * (B_DEP + p));
          }
        }
        if (warp == 9) {
          mbar_sleep(bars + 8 * (B_DEP + 1), 0);
          const char* src = reinterpret_cast<const char*>(P.w2p) + (size_t)cta * 57344;
#pragma unroll 1
          for (int i = lane; i < 448; i += 32) {
            asm volatile("prefetch.global.L2 [%0];" ::"l"(src + i * 128));
            __nanosleep(W2_GAP);
          }
        }
        TILE_COORDS;
#pragma unroll 1
        for (int t = 0; t < 4; t++) {
          nbar_sync(NB_PUB + 2 * t + warp - 9, 128 + 32);
          if (lane == 0 && t == 3) mbar_arrive(bars + 8 * B_TOP);
          if (lane == 0) { fence_async_gmem(); cnt_arrive(C_R + t * 16 + mblk); }
          __syncwarp();
        }
      }
    }
    } else {
      asm volatile("setmaxnreg.dec.sync.aligned.u32 72;");
      asm volatile("barrier.cluster.arrive.relaxed.aligned;" ::: "memory");
      const int w4 = warp - 12;
      const int p = (lane >> 3) & 1, grp = (w4 & 1) * 16 + (lane >> 4) * 8 + (lane & 7);
      const uint4 sk0 = __ldg(reinterpret_cast<const uint4*>(P.shiftk + cta * 32) + p * 2);
      const uint4 sk1 = __ldg(reinterpret_cast<const uint4*>(P.shiftk + cta * 32) + p * 2 + 1);
      const unsigned epr = cnt_peek(C_H + 8 + (cta >> 4), vz);
      asm volatile("barrier.cluster.wait.acquire.aligned;" ::: "memory");
      {
        uint32_t w[4][2];
        w[0][0] = __byte_perm(sk0.x, sk0.z, 0x5410); w[1][0] = __byte_perm(sk0.x, sk0.z, 0x7632);
        w[2][0] = __byte_perm(sk0.y, sk0.w, 0x5410); w[3][0] = __byte_perm(sk0.y, sk0.w, 0x7632);
        w[0][1] = __byte_perm(sk1.x, sk1.z, 0x5410); w[1][1] = __byte_perm(sk1.x, sk1.z, 0x7632);
        w[2][1] = __byte_perm(sk1.y, sk1.w, 0x5410); w[3][1] = __byte_perm(sk1.y, sk1.w, 0x7632);
        const uint32_t wbase = sb + (p ? SM_P1 : SM_P0) + 128 + grp * 32 + ((((grp >> 2) + 1) & 1) << 4);
        uint32_t rb[8];
#pragma unroll
        for (int r = 0; r < 8; r++) rb[r] = grp * 288 + ((rank ^ (((grp + r) >> 2) & 1)) << 4) + p * 8;
#pragma unroll 1
        for (int i = w4 >> 1; i < 8; i += 2) {
          const uint32_t kb = sb + raw_off(i), vb = kb + RAWCH;
          const uint32_t wdst = wbase + i * 1024;
          mbar_wait(bars + 8 * (B_RAW + i), 0);
          uint32_t u[9][2];
          uint2 k3 = lds64(kb + rb[4] + 4 * 32), k2 = lds64(kb + rb[5] + 5 * 32), k1 = lds64(kb + rb[6] + 6 * 32);
#pragma unroll
          for (int j = 0; j < 9; j++) {
            const int r = j ? 8 + j : 7;
            const uint2 k0 = lds64(kb + rb[r & 7] + r * 32), vv = lds64(vb + rb[(r + 4) & 7] + r * 32);
            u[j][0] = bmul2(bfma2(k0.x, w[0][0], bfma2(k1.x, w[1][0], bfma2(k2.x, w[2][0], bmul2(k3.x, w[3][0])))), vv.x);
            u[j][1] = bmul2(bfma2(k0.y, w[0][1], bfma2(k1.y, w[1][1], bfma2(k2.y, w[2][1], bmul2(k3.y, w[3][1])))), vv.y);
            k3 = k2; k2 = k1; k1 = k0;
          }
#pragma unroll
          for (int c = 0; c < 4; c++) {
            const int cp = c >> 1; const uint32_t sel = (c & 1) ? 0x7632 : 0x5410;
#pragma unroll
            for (int h = 0; h < 2; h++)
              sts128((h ? wdst ^ 16 : wdst) + c * W_PITCH,
                     make_uint4(__byte_perm(u[4 * h + 1][cp], u[4 * h][cp], sel), __byte_perm(u[4 * h + 2][cp], u[4 * h + 1][cp], sel),
                                __byte_perm(u[4 * h + 3][cp], u[4 * h + 2][cp], sel), __byte_perm(u[4 * h + 4][cp], u[4 * h + 3][cp], sel)));
          }
          __syncwarp();
          if (lane == 0) mbar_arrive(bars + 8 * (B_U + i));
          if (lane >= 30 && (i >> 1) == 1) mbar_arrive_cta(bars + 8 * (B_RE + i - 2), lane & 1);
        }
      }
      mbar_sleep(bars + 8 * (B_DEP + 1), 0);
      TILE_COORDS;
      {
        const uint4* src = reinterpret_cast<const uint4*>(g_hT + (size_t)(nblk * 64 + w4 * 16 + (lane >> 4)) * S_ + mblk * 128) + (lane & 15);
        float s1[8], s2[8];
#pragma unroll
        for (int e = 0; e < 8; e++) s1[e] = s2[e] = 0.f;
#pragma unroll 1
        for (int b = 0; b < 2; b++) {
          uint4 v[8];
#pragma unroll
          for (int j = 0; j < 8; j++) v[j] = __ldcg(src + (b * 512 + j * 2) * (S_ / 8));
#pragma unroll
          for (int j = 0; j < 8; j++)
#pragma unroll
            for (int e = 0; e < 4; e++) {
              const float a = bf_lo(u4get(v[j], e)), c = bf_hi(u4get(v[j], e));
              s1[2 * e] += a; s2[2 * e] = fmaf(a, a, s2[2 * e]); s1[2 * e + 1] += c; s2[2 * e + 1] = fmaf(c, c, s2[2 * e + 1]);
            }
        }
#pragma unroll
        for (int e = 0; e < 8; e++) { s1[e] += __shfl_xor_sync(0xffffffff, s1[e], 16); s2[e] += __shfl_xor_sync(0xffffffff, s2[e], 16); }
        if (lane < 16) {
#pragma unroll
          for (int e = 0; e < 8; e++) sts64f(sb + SM_RST + w4 * 1024 + (lane * 8 + e) * 8, s1[e], s2[e]);
        }
        nbar_sync(NB_EPI, 128);
        const int row = tid - 384;
        const uint32_t nm1 = __ldcg(reinterpret_cast<const unsigned short*>(g_ln1) + mblk * 128 + row);
        float a = 0.f, b = 0.f;
#pragma unroll
        for (int j = 0; j < 4; j++) { const float2 t = lds64f(sb + SM_RST + j * 1024 + row * 8); a += t.x; b += t.y; }
        g_st2[(mblk * 8 + nblk) * 128 + row] = make_float2(a, b);
        nbar_sync(NB_EPI, 128);
        if (row == 0) cnt_arrive(C_ST + mblk);
        cnt_wait(C_ST + mblk, ep1 * 8);
        a = b = 0.f;
#pragma unroll
        for (int j = 0; j < 8; j++) { const float2 t = __ldcg(g_st2 + (mblk * 8 + j) * 128 + row); a += t.x; b += t.y; }
        a *= (1.f / D_);
        const float rx = rsqrtf(fmaxf(fmaf(-a, a, b * (1.f / D_)), 0.f) + LN_EPS);
        const uint32_t rs = pack_bf16(rx, rx);
        const float mr = -a * bf_lo(rs);
        sts128(sb + SM_RSF + row * 16, make_uint4(rs, pack_bf16(mr, mr), nm1 << 16, 0));
        __syncwarp();
        if (lane == 0) mbar_arrive(bars + 8 * B_CSB);
        if (w4 == 0) {
#pragma unroll 1
          for (int t = 0; t < 4; t++) {
            if (t == 3) mbar_sleep(bars + 8 * B_TOP, 0);
            cnt_wait(C_R + t * 16 + mblk, ep1 * 16);
            if (lane == 0) mbar_arrive(bars + 8 * (B_DEP + 2 + t));
          }
        }
      }
    }
  } else {
    asm volatile("barrier.cluster.arrive.relaxed.aligned;" ::: "memory");
    asm volatile("setmaxnreg.inc.sync.aligned.u32 200;");
    const int wg = warp >> 2, w4 = warp & 3;
    const int g = lane >> 2, c4 = lane & 3;
    asm volatile("barrier.cluster.wait.acquire.aligned;" ::: "memory");
    {
      const int x0 = 32 + 8 * w4 + g - 2 * c4, x1 = x0 + 32;
      const uint32_t we = sb + wg * 2 * W_PITCH + 4 * (x0 ^ (((x0 >> 5) & 1) << 2)), wo = sb + wg * 2 * W_PITCH + 4 * (x1 ^ (((x1 >> 5) & 1) << 2));
      const uint32_t kd = (uint32_t)desc(P_K + K_PAD - 64, 64, 128, 0) + wg * (2 * K_PITCH / 16);
      const uint32_t prow = sb + wg * 2 * W_PITCH + w4 * 512 + lane * 16;
      auto ln1 = [&]() {
        mbar_wait(bars + 8 * B_XR, 0);
        const uint32_t xa = sb + (warp < 5 ? SM_X0 + warp * 4096 : warp < 7 ? SM_X1 + (warp - 5) * 4096 : SM_X2) + lane * 16;
        float s[2], v[2], s2[2][2] = {{0.f, 0.f}, {0.f, 0.f}}, v2[2][2] = {{0.f, 0.f}, {0.f, 0.f}};
        uint4 x[2] = {lds128(xa), lds128(xa + 2048)};
#pragma unroll
        for (int j = 0; j < 4; j++) {
#pragma unroll
          for (int r = 0; r < 2; r++) {
            const uint4 c = x[r];
            if (j < 3) x[r] = lds128(xa + r * 2048 + (j + 1) * 512);
#pragma unroll
            for (int e = 0; e < 4; e++) {
              const float a = bf_lo(u4get(c, e)), b = bf_hi(u4get(c, e));
              s2[r][0] += a; s2[r][1] += b; v2[r][0] = fmaf(a, a, v2[r][0]); v2[r][1] = fmaf(b, b, v2[r][1]);
            }
          }
        }
#pragma unroll
        for (int r = 0; r < 2; r++) { s[r] = s2[r][0] + s2[r][1]; v[r] = v2[r][0] + v2[r][1]; }
        float t0 = (lane & 16) ? s[1] : s[0], t1 = (lane & 16) ? v[1] : v[0];
        t0 += __shfl_xor_sync(0xffffffff, (lane & 16) ? s[0] : s[1], 16);
        t1 += __shfl_xor_sync(0xffffffff, (lane & 16) ? v[0] : v[1], 16);
        float t = (lane & 8) ? t1 : t0;
        t += __shfl_xor_sync(0xffffffff, (lane & 8) ? t0 : t1, 8);
        t += __shfl_xor_sync(0xffffffff, t, 4); t += __shfl_xor_sync(0xffffffff, t, 2); t += __shfl_xor_sync(0xffffffff, t, 1);
        const float sq = __shfl_down_sync(0xffffffff, t, 8);
        if ((lane & 15) == 0) {
          const float mean = t * (1.f / D_);
          const float rs = rsqrtf(fmaxf(fmaf(-mean, mean, sq * (1.f / D_)), 0.f) + LN_EPS);
          __nv_bfloat16* dst = g_ln1 + cta * 16 + warp * 2 + (lane >> 4);
          dst[0] = __float2bfloat16(-mean); dst[S_] = __float2bfloat16(rs);
        }
        nbar_arrive(NB_LN, 256 + 32);
        if (lane == 0) mbar_arrive(bars + 8 * B_XD);
      };
      ConvArgs A;
      A.ubar = bars + 8 * B_U;
      {
        mbar_wait(bars + 8 * B_KP, 0);
        A.we = we + SM_P0; A.wo = wo + SM_P0; A.kd = kd + SM_P0 / 16;
        float cy[4] = {0.f, 0.f, 0.f, 0.f};
        A.pb = prow + SM_R0;
        conv_pair<0>(cy, A, ln1);
        mbar_wait(bars + 8 * (B_KF + 1), 0);
        A.pb = prow + SM_P0;
        conv_pair<4>(cy, A, ln1);
        mbar_wait(bars + 8 * (B_KP + 1), 0);
      }
#pragma unroll 1
      for (int p = 0; p < 2; p++) {
        {
          const int cc = p;
          A.we = we + SM_P1 + cc * W_PITCH; A.wo = wo + SM_P1 + cc * W_PITCH; A.kd = kd + (SM_P1 + cc * K_PITCH) / 16;
          A.pb = prow + SM_PL1 + cc * W_PITCH; A.pb2 = prow + SM_P1 + cc * W_PITCH;
          float d[8][16], c0 = 0.f, c1 = 0.f;
          uint32_t a[6][4];
          ConvSingle<0, 0>::run(d, a, c0, c1, A);
        }
        mbar_wait(bars + 8 * B_Q, 0);
        uint2 xq[8];
#pragma unroll
        for (int j = 0; j < 8; j++) xq[j] = lds64(sb + SM_Q + warp * Q_CH + lane * 144 + p * 8 + j * 16);
        const uint4 nm = lds128(sb + SM_ST + tid * 16), rs = lds128(sb + SM_ST + 4096 + tid * 16);
        uint32_t xp[4][4], qn[4][4];
#pragma unroll
        for (int c = 0; c < 4; c++)
#pragma unroll
          for (int e = 0; e < 4; e++) {
            xp[c][e] = badd2(__byte_perm((c >> 1) ? xq[2 * e].y : xq[2 * e].x, (c >> 1) ? xq[2 * e + 1].y : xq[2 * e + 1].x, (c & 1) ? 0x7632 : 0x5410), u4get(nm, e));
            qn[c][e] = bmul2(xp[c][e], u4get(rs, e));
          }
        uint32_t pa[4];
#pragma unroll
        for (int x = 0; x < 4; x++) {
          const int ch = tid - x;
          pa[x] = sb + (ch >= 128 ? (p ? SM_P1 : SM_P0) : (p ? SM_PL1 : SM_R0)) + (ch < 0 ? 8192 : ((ch >> 5) & 3) * 2048 + x * 512 + ((ch & 31) << 4));
        }
        nbar_sync(NB_CONS, 256);
        uint4 pv[4][4];
#pragma unroll
        for (int c = 0; c < 4; c++)
#pragma unroll
          for (int x = 0; x < 4; x++) pv[c][x] = lds128(pa[x] + c * W_PITCH);
        __syncwarp();
        if (lane < 2) mbar_arrive_cta(bars + 8 * (B_FREE + p), lane);
#pragma unroll
        for (int c = 0; c < 4; c++) {
          uint32_t hh[4];
#pragma unroll
          for (int e = 0; e < 4; e++) {
            const uint32_t y = badd2(badd2(u4get(pv[c][0], e), u4get(pv[c][1], e)), badd2(u4get(pv[c][2], e), u4get(pv[c][3], e)));
            hh[e] = bfma2(qn[c][e], y, xp[c][e]);
          }
          *reinterpret_cast<uint4*>(g_hT + (size_t)(p * 512 + cta * 4 + c) * S_ + tid * 8) = make_uint4(hh[0], hh[1], hh[2], hh[3]);
        }
        nbar_arrive(NB_PUBH + p, 256 + 32);
      }
    }
    int it;
    uint4 st2;
    float nm0, nm8;
    uint8_t* rdst;
    const uint32_t csb = sb + SM_CSB + c4 * 16;
    const uint64_t dA1 = desc(0, 8192, 1024, 1) + wg * 512, dA2 = desc(0, 128, 1024, 0) + wg * 512, dB = desc(16384, 4096, 1024, 1);
    constexpr int DS = STAGE / 16;
    auto full = [&](int it_) { mbar_wait(bars + 8 * (B_FULL + (it_ & 3)), (it_ >> 2) & 1); };
    auto release = [&](int it_) { if (lane < 2) mbar_arrive_cta(bars + 8 * (B_EMPTY + (it_ & 3)), lane); };
    uint32_t pk0[32], pk0b[32];
    {
      float d[64], d2[64];
      auto kblock = [&](int it_, bool first) {
        const uint64_t da = dA1 + (it_ & 3) * DS, db = dB + (it_ & 3) * DS;
        full(it_);
        wg_fence();
#pragma unroll
        for (int k = 0; k < 4; k++) {
          if (k == 1 && !first) { wg_commit(); wg_wait<1>(); release(it_ - 1); }
          if (first && k == 0) { wg_ss128t_first(d, da, db); wg_ss128t_first(d2, da, db + 512); continue; }
          wg_ss128t(d, da + k * 128, db + (k >> 1) * 1024 + (k & 1) * 128);
          wg_ss128t(d2, da + k * 128, db + 512 + (k >> 1) * 1024 + (k & 1) * 128);
        }
        wg_commit();
      };
      kblock(0, true);
#pragma unroll 1
      for (it = 1; it < 16; it++) {
        if (it == 15 && wg != LEAD) nbar_sync(NB_CONS, 256);
        kblock(it, false);
      }
      if (wg == LEAD) nbar_arrive(NB_CONS, 256);
      wg_wait<0>();
      pin(d); pin(d2);
      release(15);
      pack_acc(d, pk0);
      pack_acc(d2, pk0b);
    }
    float dt[96];
    {
      float (&d)[96] = dt;
      auto kblock = [&](int it_, bool first) {
        const uint64_t da = dA1 + (it_ & 3) * DS, db = dB + (it_ & 3) * DS;
        full(it_);
        wg_fence();
#pragma unroll
        for (int k = 0; k < 4; k++) {
          if (k == 1 && !first) { wg_commit(); wg_wait<1>(); release(it_ - 1); }
          if (first && k == 0) wg_ss192_first(d, da, db);
          else wg_ss<192>(d, da + k * 128, db + (k >> 1) * 1024 + (k & 1) * 128);
        }
        wg_commit();
      };
#pragma unroll
      for (int t = 0; t < RS_N; t++) {
        kblock(16 + t, t == 0);
        mbar_wait(bars + 8 * B_CSB, 0);
        if (t == 0) {
          const uint4 t0 = lds128(sb + SM_RSF + (warp * 16 + g) * 16), t1 = lds128(sb + SM_RSF + (warp * 16 + g + 8) * 16);
          st2 = make_uint4(t0.x, t0.y, t1.x, t1.y);
          nm0 = __uint_as_float(t0.z); nm8 = __uint_as_float(t1.z);
          TILE_COORDS;
          rdst = reinterpret_cast<uint8_t*>(g_r) + (uint32_t)((mblk * 56 + nblk * 7) * 16384 + warp * 2048 + lane * 4);
        }
        const int q0 = t ? rs_done(t - 1) : 0, q1 = rs_done(t);
        if (q0 < 16) r_store(pk0, q0, q1, csb, st2, rdst);
        else r_store(pk0b, q0 - 16, q1 - 16, csb + 512, st2, rdst + 2 * 16384);
        if ((q1 & 15) == 0) nbar_arrive(NB_PUB + (q1 >> 3) - 2 + wg, 128 + 32);
      }
#pragma unroll 1
      for (it = 16 + RS_N; it < 32; it++) {
        kblock(it, false);
      }
    }
    {
      float d[64];
      auto kblock = [&](int s, int par, int prev, bool first) {
        const uint64_t da = dA2 + s * (STAGE2 / 16), db = dB + s * (STAGE2 / 16);
        mbar_wait(bars + 8 * (B_FULL2 + s), par);
        wg_fence();
#pragma unroll
        for (int k = 0; k < 4; k++) {
          if (first && k == 0) wg_ss128_first(d, da, db);
          else wg_ss<128>(d, da + k * 16, db + (k >> 1) * 512 + (k & 1) * 128);
        }
        wg_commit();
        wg_wait<1>();
        if (prev >= 0 && lane < 2) mbar_arrive_cta(bars + 8 * prev, lane);
      };
      kblock(0, 0, B_EMPTY + 3, true);
      pin(dt);
      mbar_wait(bars + 8 * B_CSB1, 0);
      int s = 1, par = 0, ps = 0;
      it = 1;
      auto steps = [&](int n) {
#pragma unroll 1
        for (; it < n; it++) {
          kblock(s, par, it < 57 - NSTAGE2 ? B_EMPTY2 + ps : -1, false);
          ps = s;
          if (++s == NSTAGE2) { s = 0; par ^= 1; }
        }
      };
#pragma unroll
      for (int t = 0; t < 12; t++) {
        r_store(dt, 2 * t, csb + 1024, st2, rdst + 4 * 16384);
        if (t == 3 || t == 11) nbar_arrive(NB_PUB + (t == 3 ? 4 : 6) + wg, 128 + 32);
        steps(t < 11 ? 1 + (t + 1) * R1_EVERY / 4 : RES_END - 8);
      }
      float ad[64];
      const int kr = (lane >> 4) * 4 + (lane & 3);
      const uint32_t rb = sb + NSTAGE * STAGE + wg * 2048 + ((lane >> 2) & 1) * 4096 + kr * 128 + (((w4 * 2 + ((lane >> 3) & 1)) ^ kr) << 4);
      TILE_COORDS;
      mbar_wait(bars + 8 * B_RES, 0);
#pragma unroll
      for (int q = 0; q < 8; q++) {
        uint32_t r0, r1, r2, r3;
        ldsm4t(rb + (q >> 1) * 8192 + (q & 1) * 1024, r0, r1, r2, r3);
        const uint4 bb = lds128(sb + SM_B2 + q * 64 + c4 * 16);
        steps(RES_END - 7 + q);
        ad[8 * q] = bf_lo(r0) - nm0 + __uint_as_float(bb.x); ad[8 * q + 1] = bf_hi(r0) - nm0 + __uint_as_float(bb.y);
        ad[8 * q + 2] = bf_lo(r1) - nm8 + __uint_as_float(bb.x); ad[8 * q + 3] = bf_hi(r1) - nm8 + __uint_as_float(bb.y);
        ad[8 * q + 4] = bf_lo(r2) - nm0 + __uint_as_float(bb.z); ad[8 * q + 5] = bf_hi(r2) - nm0 + __uint_as_float(bb.w);
        ad[8 * q + 6] = bf_lo(r3) - nm8 + __uint_as_float(bb.z); ad[8 * q + 7] = bf_hi(r3) - nm8 + __uint_as_float(bb.w);
        anchor8(&ad[8 * q], vc);
      }
      steps(wg != LEAD ? TAIL_HOLD : TAIL_GO);
      if (wg != LEAD) nbar_sync(NB_CONS, 256); else nbar_arrive(NB_CONS, 256);
      steps(56);
      wg_wait<0>();
      pin(d);
      const uint32_t ob = sb + NSTAGE * STAGE + warp * 4096;
      const uint32_t orow = ob + (lane & 15) * 128;
#pragma unroll
      for (int hf = 0; hf < 2; hf++) {
#pragma unroll
        for (int q = 8 * hf; q < 8 * hf + 8; q += 2) {
          const int qq = q + (lane >> 4);
          stsm4(orow + hf * 2048 + (((qq & 7) ^ (lane & 7)) << 4),
                pack_bf16(d[4 * q] + ad[4 * q], d[4 * q + 1] + ad[4 * q + 1]), pack_bf16(d[4 * q + 2] + ad[4 * q + 2], d[4 * q + 3] + ad[4 * q + 3]),
                pack_bf16(d[4 * q + 4] + ad[4 * q + 4], d[4 * q + 5] + ad[4 * q + 5]), pack_bf16(d[4 * q + 6] + ad[4 * q + 6], d[4 * q + 7] + ad[4 * q + 7]));
        }
        fence_async_smem();
        __syncwarp();
        if (lane == 0) tma2d_store(&P.out, nblk * 128 + hf * 64, mblk * 128 + warp * 16, ob + hf * 2048);
      }
      if (lane == 0) {
        asm volatile("cp.async.bulk.commit_group;" ::: "memory");
        asm volatile("cp.async.bulk.wait_group.read 0;" ::: "memory");
      }
    }
  }
}

typedef CUresult (*EncFn)(CUtensorMap*, CUtensorMapDataType, cuuint32_t, void*, const cuuint64_t*, const cuuint64_t*, const cuuint32_t*,
                          const cuuint32_t*, CUtensorMapInterleave, CUtensorMapSwizzle, CUtensorMapL2promotion, CUtensorMapFloatOOBfill);

void enc(EncFn fn, CUtensorMap* m, const void* p, int rank, cuuint64_t d0, cuuint64_t d1, cuuint64_t d2, cuuint64_t s1, cuuint64_t s2,
         cuuint32_t b0, cuuint32_t b1, cuuint32_t b2, CUtensorMapSwizzle sw, cuuint64_t d3 = 1, cuuint64_t s3 = 0, cuuint32_t b3 = 1) {
  cuuint64_t gd[4] = {d0, d1, d2, d3}, gs[3] = {s1, s2, s3};
  cuuint32_t bd[4] = {b0, b1, b2, b3}, es[4] = {1, 1, 1, 1};
  fn(m, CU_TENSOR_MAP_DATA_TYPE_BFLOAT16, rank, const_cast<void*>(p), gd, gs, bd, es, CU_TENSOR_MAP_INTERLEAVE_NONE, sw,
     CU_TENSOR_MAP_L2_PROMOTION_L2_128B, CU_TENSOR_MAP_FLOAT_OOB_FILL_NONE);
}

}

extern "C" void kernel_launch(void* const* d_in, const int* in_sizes, int n_in, void* d_out, int out_size) {
  (void)in_sizes; (void)n_in; (void)out_size;
  static EncFn fn = nullptr;
  static void *hT = nullptr, *rp = nullptr;
  if (!fn) {
    void* f = nullptr;
    cudaDriverEntryPointQueryResult qr;
    cudaGetDriverEntryPoint("cuTensorMapEncodeTiled", &f, cudaEnableDefault, &qr);
    fn = (EncFn)f;
    cudaGetSymbolAddress(&hT, g_hT);
    cudaGetSymbolAddress(&rp, g_r);
    cudaFuncSetAttribute(fused_kernel, cudaFuncAttributeMaxDynamicSharedMemorySize, SMEM_BYTES);
  }
  typedef const __nv_bfloat16* bp;
  Params P;
  P.q = (bp)d_in[0]; P.shiftk = (bp)d_in[3]; P.ssmk = (bp)d_in[4]; P.ssmD = (bp)d_in[5];
  P.b1 = (bp)d_in[8]; P.w2p = (bp)d_in[9]; P.b2 = (bp)d_in[10];
  const CUtensorMapSwizzle NOSW = CU_TENSOR_MAP_SWIZZLE_NONE, SW128 = CU_TENSOR_MAP_SWIZZLE_128B;
  enc(fn, &P.k3, d_in[1], 3, D_, 8, S_ / 8, D_ * 2, 8 * D_ * 2, 16, 9, 33, CU_TENSOR_MAP_SWIZZLE_32B);
  enc(fn, &P.v3, d_in[2], 3, D_, 8, S_ / 8, D_ * 2, 8 * D_ * 2, 16, 9, 33, CU_TENSOR_MAP_SWIZZLE_32B);
  enc(fn, &P.q3, d_in[0], 3, D_, 8, S_ / 8, D_ * 2, 8 * D_ * 2, 8, 9, 32, NOSW);
  enc(fn, &P.hT, hT, 3, 64, D_, S_ / 64, S_ * 2, 128, 64, 64, 2, SW128);
  enc(fn, &P.hR, hT, 3, 64, D_, S_ / 64, S_ * 2, 128, 64, 16, 2, SW128);
  enc(fn, &P.w1a, d_in[7], 4, 64, 8, D_ / 8, F_ * 2, 8 * F_ * 2, 64, 4, 8, SW128, F_ / 64, 128, 4);
  enc(fn, &P.w1b, d_in[7], 4, 64, 8, D_ / 8, F_ * 2, 8 * F_ * 2, 64, 4, 8, SW128, F_ / 64, 128, 3);
  enc(fn, &P.w2, d_in[9], 3, 64, F_, D_ / 64, D_ * 2, 128, 64, 32, 2, SW128);
  enc(fn, &P.r, rp, 3, 64, 128, 16 * 56, 128, 16384, 64, 128, 1, NOSW);
  enc(fn, &P.out, d_out, 2, D_, S_, 1, D_ * 2, 0, 64, 16, 1, SW128);

  cudaLaunchConfig_t cfg = {};
  cfg.gridDim = dim3(NCTA + NXTRA); cfg.blockDim = dim3(NTHREADS); cfg.dynamicSmemBytes = SMEM_BYTES; cfg.stream = cudaStreamPerThread;
  cudaLaunchAttribute at[1];
  at[0].id = cudaLaunchAttributeClusterDimension; at[0].val.clusterDim.x = 2; at[0].val.clusterDim.y = 1; at[0].val.clusterDim.z = 1;
  cfg.attrs = at; cfg.numAttrs = 1;
  cudaLaunchKernelEx(&cfg, fused_kernel, P);
}
```
